```python
import torch

def _softmax(x, axis=-1):
    return torch.softmax(x, dim=axis)
def _gelu(x):
    return torch.nn.functional.gelu(x, approximate="tanh")
def _silu(x):
    return torch.nn.functional.silu(x)
def _sigmoid(x):
    return torch.sigmoid(x)
def _layernorm(x, axis=-1, eps=1e-5):
    m = x.mean(dim=axis, keepdim=True)
    v = x.var(dim=axis, keepdim=True, unbiased=False)
    return (x - m) / torch.sqrt(v + eps)
def _scatter_add(tgt, idx, src, axis=0):
    return tgt.clone().index_add_(axis, idx, src)
def _segment_sum(src, seg, n):
    out = torch.zeros((n,) + src.shape[1:], dtype=src.dtype)
    return out.index_add_(0, seg, src)
def _pad(x, pw):
    flat = tuple(v for pair in reversed(pw) for v in pair)
    return torch.nn.functional.pad(x, flat)

kernel_name = 'standalone__fused_io_aware_attn__prompt'

def setup_inputs():

    _w = (lambda a: (lambda t: t.to(torch.bfloat16) if t.is_floating_point() else t)(torch.as_tensor(a)))
    B, H, S = 1, 32, 2048
    Dh = max(1, 512 // 32)
    return {
        "q": _w((lambda *s: torch.randn(*s, dtype=torch.bfloat16) * 0.8)(B, H, S, Dh)),
        "k": _w((lambda *s: torch.randn(*s, dtype=torch.bfloat16) * 0.8)(B, H, S, Dh)),
        "v": _w((lambda *s: torch.randn(*s, dtype=torch.bfloat16) * 0.05)(B, H, S, Dh)),
    }

def reference(q, k, v):
    scale = q.shape[-1] ** -0.5
    s = torch.einsum('bhqd,bhkd->bhqk', q, k) * scale
    p = _softmax(s, axis=-1)
    return torch.einsum('bhqk,bhkd->bhqd', p, v)
```

```cpp
#include <cuda_runtime.h>
#include <cuda_bf16.h>
#include <cuda_fp16.h>
#include <stdint.h>

#define MUFU_MASK 0x4924
#define SYNC2 0

#define EARLY 2

namespace {

constexpr int S_LEN = 2048;
constexpr int DH = 16;
constexpr int NHEAD = 32;
constexpr int ROWS_PER_CTA = 512;
constexpr int NTHREADS = 512;
constexpr int K_BYTES = S_LEN * DH * 2;
constexpr int V_BYTES = S_LEN * DH * 2;
constexpr int ONES_BYTES = 512;
constexpr int SMEM_BYTES = K_BYTES + V_BYTES + ONES_BYTES;

__device__ __forceinline__ void wg_fence() { asm volatile("wgmma.fence.sync.aligned;" ::: "memory"); }
__device__ __forceinline__ void wg_commit() { asm volatile("wgmma.commit_group.sync.aligned;" ::: "memory"); }
template<int N> __device__ __forceinline__ void wg_wait() { asm volatile("wgmma.wait_group.sync.aligned %0;" :: "n"(N) : "memory"); }

__device__ __forceinline__ uint64_t make_desc(uint32_t saddr, uint32_t lbo, uint32_t sbo) {
    return (uint64_t)((saddr & 0x3FFFF) >> 4) | ((uint64_t)((lbo & 0x3FFFF) >> 4) << 16) | ((uint64_t)((sbo & 0x3FFFF) >> 4) << 32) | (3ull << 62);
}
__device__ __forceinline__ void cp_async16(uint32_t saddr, const void* g) {
    asm volatile("cp.async.cg.shared.global [%0], [%1], 16;" :: "r"(saddr), "l"(g) : "memory");
}
template<int N> __device__ __forceinline__ void fence_f(float (&a)[N]) {
#pragma unroll
    for (int i = 0; i < N; i++) asm volatile("" : "+f"(a[i]) :: "memory");
}
template<int N> __device__ __forceinline__ void fence_u(uint32_t (&a)[N]) {
#pragma unroll
    for (int i = 0; i < N; i++) asm volatile("" : "+r"(a[i]) :: "memory");
}
__device__ __forceinline__ void wgmma_qk_n64_bf16(float (&d)[32], const uint32_t (&a)[4], uint64_t descB) {
  asm volatile("{\n.reg .pred p;\nsetp.ne.b32 p, 0, 0;\n"
    "wgmma.mma_async.sync.aligned.m64n64k16.f32.bf16.bf16 {%0, %1, %2, %3, %4, %5, %6, %7, %8, %9, %10, %11, %12, %13, %14, %15, %16, %17, %18, %19, %20, %21, %22, %23, %24, %25, %26, %27, %28, %29, %30, %31}, {%32, %33, %34, %35}, %36, p, 1, 1, 0;\n}\n"
    : "=f"(d[0]), "=f"(d[1]), "=f"(d[2]), "=f"(d[3]), "=f"(d[4]), "=f"(d[5]), "=f"(d[6]), "=f"(d[7]), "=f"(d[8]), "=f"(d[9]), "=f"(d[10]), "=f"(d[11]), "=f"(d[12]), "=f"(d[13]), "=f"(d[14]), "=f"(d[15]), "=f"(d[16]), "=f"(d[17]), "=f"(d[18]), "=f"(d[19]), "=f"(d[20]), "=f"(d[21]), "=f"(d[22]), "=f"(d[23]), "=f"(d[24]), "=f"(d[25]), "=f"(d[26]), "=f"(d[27]), "=f"(d[28]), "=f"(d[29]), "=f"(d[30]), "=f"(d[31])
    : "r"(a[0]), "r"(a[1]), "r"(a[2]), "r"(a[3]), "l"(descB));
}
__device__ __forceinline__ void wgmma_pv_n24_bf16(float (&d)[12], uint32_t a0, uint32_t a1, uint32_t a2, uint32_t a3, uint64_t descB) {
  asm volatile("{\n.reg .pred p;\nsetp.eq.b32 p, 0, 0;\n"
    "wgmma.mma_async.sync.aligned.m64n24k16.f32.bf16.bf16 {%0, %1, %2, %3, %4, %5, %6, %7, %8, %9, %10, %11}, {%12, %13, %14, %15}, %16, p, 1, 1, 1;\n}\n"
    : "+f"(d[0]), "+f"(d[1]), "+f"(d[2]), "+f"(d[3]), "+f"(d[4]), "+f"(d[5]), "+f"(d[6]), "+f"(d[7]), "+f"(d[8]), "+f"(d[9]), "+f"(d[10]), "+f"(d[11])
    : "r"(a0), "r"(a1), "r"(a2), "r"(a3), "l"(descB));
}

__device__ __forceinline__ float ex2f(float x) { float e; asm("ex2.approx.ftz.f32 %0, %1;" : "=f"(e) : "f"(x)); return e; }
__device__ __forceinline__ uint32_t pack_bf16x2(float lo, float hi) {
    uint32_t r; asm("cvt.rn.bf16x2.f32 %0, %1, %2;" : "=r"(r) : "f"(hi), "f"(lo)); return r;
}
__device__ __forceinline__ uint32_t exp_mufu(float s0, float s1) { return pack_bf16x2(ex2f(s0), ex2f(s1)); }

__device__ __forceinline__ uint32_t exp_poly(float s0, float s1, float bias, uint32_t chalf, uint32_t cmu) {
    const float mul = __uint_as_float(128u);
    float t0 = __fmaf_rn(s0, mul, bias), t1 = __fmaf_rn(s1, mul, bias);
    uint32_t pl; asm("cvt.pack.sat.s16.s32 %0, %1, %2;" : "=r"(pl) : "r"(__float_as_uint(t1)), "r"(__float_as_uint(t0)));
    uint32_t z, e, p;
    asm("lop3.b32 %0, %1, 0x007F007F, %2, 0xEA;" : "=r"(z) : "r"(pl), "r"(chalf));
    asm("lop3.b32 %0, %1, 0xFF80FF80, %2, 0xEA;" : "=r"(e) : "r"(pl), "r"(cmu));
    asm("fma.rn.relu.bf16x2 %0, %1, %2, %3;" : "=r"(p) : "r"(pl), "r"(z), "r"(e));
    return p;
}

__host__ __device__ constexpr bool kstep_is_mufu(int ks16) { return (MUFU_MASK >> ks16) & 1; }

template<int SUB>
__device__ __forceinline__ void process_block(const float (&S)[32], uint32_t (&P)[16], float bias, uint32_t chalf, uint32_t cmu) {
#pragma unroll
    for (int ks = 0; ks < 4; ks++) {
#pragma unroll
        for (int j = 0; j < 4; j++) {
            if (kstep_is_mufu(SUB * 4 + ks)) P[ks * 4 + j] = exp_mufu(S[ks * 8 + 2 * j], S[ks * 8 + 2 * j + 1]);
            else                             P[ks * 4 + j] = exp_poly(S[ks * 8 + 2 * j], S[ks * 8 + 2 * j + 1], bias, chalf, cmu);
        }
    }
}

constexpr uint64_t VSTEP = 32ull - (32ull << 16);

__device__ __forceinline__ void issue_pv(float (&Oa)[12], const uint32_t (&P)[16], uint64_t descV) {
#pragma unroll
    for (int ks = 0; ks < 4; ks++) wgmma_pv_n24_bf16(Oa, P[ks * 4], P[ks * 4 + 1], P[ks * 4 + 2], P[ks * 4 + 3], descV + ks * VSTEP);
}

__device__ __forceinline__ uint32_t scale_bf16x2(uint32_t x, float c) {
    return pack_bf16x2(__uint_as_float(x << 16) * c, __uint_as_float(x & 0xFFFF0000u) * c);
}

#define STEP(SUB, PCUR, NSUB, PNEXT, KOFF) \
    wg_fence(); \
    wgmma_qk_n64_bf16(S, qa, descK + (KOFF)); \
    wg_commit(); \
    issue_pv(Oa, PCUR, descV + (SUB) * 4 * VSTEP); \
    wg_commit(); \
    wg_wait<1>(); \
    fence_f(S); \
    process_block<NSUB>(S, PNEXT, bias, chalf, cmu); \
    fence_u(PNEXT); \
    wg_wait<0>(); \
    fence_u(PCUR);

__device__ __forceinline__ void mma_bf16(float (&d)[4], const uint32_t (&a)[4], uint32_t b0, uint32_t b1) {
    asm volatile("mma.sync.aligned.m16n8k16.row.col.f32.bf16.bf16.f32 {%0,%1,%2,%3}, {%4,%5,%6,%7}, {%8,%9}, {%0,%1,%2,%3};"
                 : "+f"(d[0]), "+f"(d[1]), "+f"(d[2]), "+f"(d[3]) : "r"(a[0]), "r"(a[1]), "r"(a[2]), "r"(a[3]), "r"(b0), "r"(b1));
}
__device__ __noinline__ void safe_rows(const uint32_t* __restrict__ q32, const uint32_t* __restrict__ k32,
                                       const unsigned short* __restrict__ v16, uint32_t* __restrict__ o32) {
    const int lane = threadIdx.x & 31, g = lane >> 2, t = lane & 3;
    const float c = 0.25f * 1.4426950408889634f;
    uint32_t qa[4] = {q32[t], q32[64 + t], q32[4 + t], q32[64 + 4 + t]};
    float m0 = -INFINITY, m1 = -INFINITY, l0 = 0.f, l1 = 0.f;
    float o0[4] = {0.f, 0.f, 0.f, 0.f}, o1[4] = {0.f, 0.f, 0.f, 0.f};
#pragma unroll 1
    for (int k0 = 0; k0 < S_LEN; k0 += 16) {
        float sa[4] = {0.f, 0.f, 0.f, 0.f}, sb[4] = {0.f, 0.f, 0.f, 0.f};
        mma_bf16(sa, qa, k32[(k0 + g) * 8 + t], k32[(k0 + g) * 8 + 4 + t]);
        mma_bf16(sb, qa, k32[(k0 + 8 + g) * 8 + t], k32[(k0 + 8 + g) * 8 + 4 + t]);
#pragma unroll
        for (int i = 0; i < 4; i++) { sa[i] *= c; sb[i] *= c; }
        float n0 = fmaxf(fmaxf(sa[0], sa[1]), fmaxf(sb[0], sb[1])), n1 = fmaxf(fmaxf(sa[2], sa[3]), fmaxf(sb[2], sb[3]));
        n0 = fmaxf(n0, __shfl_xor_sync(0xffffffffu, n0, 1)); n0 = fmaxf(n0, __shfl_xor_sync(0xffffffffu, n0, 2));
        n1 = fmaxf(n1, __shfl_xor_sync(0xffffffffu, n1, 1)); n1 = fmaxf(n1, __shfl_xor_sync(0xffffffffu, n1, 2));
        n0 = fmaxf(n0, m0); n1 = fmaxf(n1, m1);
        const float u0 = (n0 == -INFINITY) ? 0.f : n0, u1 = (n1 == -INFINITY) ? 0.f : n1;
        const float c0 = ex2f(m0 - u0), c1 = ex2f(m1 - u1);
        m0 = n0; m1 = n1;
        uint32_t pa[4];
        pa[0] = exp_mufu(sa[0] - u0, sa[1] - u0); pa[1] = exp_mufu(sa[2] - u1, sa[3] - u1);
        pa[2] = exp_mufu(sb[0] - u0, sb[1] - u0); pa[3] = exp_mufu(sb[2] - u1, sb[3] - u1);
        l0 = l0 * c0 + (__uint_as_float(pa[0] << 16) + __uint_as_float(pa[0] & 0xFFFF0000u) + __uint_as_float(pa[2] << 16) + __uint_as_float(pa[2] & 0xFFFF0000u));
        l1 = l1 * c1 + (__uint_as_float(pa[1] << 16) + __uint_as_float(pa[1] & 0xFFFF0000u) + __uint_as_float(pa[3] << 16) + __uint_as_float(pa[3] & 0xFFFF0000u));
        o0[0] *= c0; o0[1] *= c0; o0[2] *= c1; o0[3] *= c1;
        o1[0] *= c0; o1[1] *= c0; o1[2] *= c1; o1[3] *= c1;
        const unsigned short* vp = v16 + (k0 + 2 * t) * 16 + g;
        mma_bf16(o0, pa, (uint32_t)vp[0] | ((uint32_t)vp[16] << 16), (uint32_t)vp[128] | ((uint32_t)vp[144] << 16));
        mma_bf16(o1, pa, (uint32_t)vp[8] | ((uint32_t)vp[24] << 16), (uint32_t)vp[136] | ((uint32_t)vp[152] << 16));
    }
    l0 += __shfl_xor_sync(0xffffffffu, l0, 1); l0 += __shfl_xor_sync(0xffffffffu, l0, 2);
    l1 += __shfl_xor_sync(0xffffffffu, l1, 1); l1 += __shfl_xor_sync(0xffffffffu, l1, 2);
    const float r0 = 1.0f / l0, r1 = 1.0f / l1;
    o32[t] = pack_bf16x2(o0[0] * r0, o0[1] * r0);       o32[64 + t] = pack_bf16x2(o0[2] * r1, o0[3] * r1);
    o32[4 + t] = pack_bf16x2(o1[0] * r0, o1[1] * r0);   o32[64 + 4 + t] = pack_bf16x2(o1[2] * r1, o1[3] * r1);
}

__global__ void __launch_bounds__(NTHREADS, 1)
attn_kernel(const __nv_bfloat16* __restrict__ Q, const __nv_bfloat16* __restrict__ K,
            const __nv_bfloat16* __restrict__ V, __nv_bfloat16* __restrict__ O) {
    extern __shared__ __align__(1024) uint8_t smem[];
    const int tid = threadIdx.x;
    const int head = blockIdx.x >> 2;
    const int rb = blockIdx.x & 3;
    const uint32_t sK = (uint32_t)__cvta_generic_to_shared(smem);
    const uint32_t sV = sK + K_BYTES;
    const int wg = tid >> 7, warp = (tid >> 5) & 3, lane = tid & 31;
    const int g = lane >> 2, t = lane & 3;

    const float qscale = 0.25f * 1.4426950408889634f;
    const size_t rowbase = (size_t)head * S_LEN + rb * ROWS_PER_CTA + wg * 128 + warp * 16 + g;
    const uint32_t* q32 = reinterpret_cast<const uint32_t*>(Q + rowbase * DH);
    uint32_t qa[4], qb[4];
    qa[0] = __ldg(q32 + t); qa[1] = __ldg(q32 + 64 + t); qa[2] = __ldg(q32 + 4 + t); qa[3] = __ldg(q32 + 64 + 4 + t);
    const uint4* gK = reinterpret_cast<const uint4*>(K + (size_t)head * S_LEN * DH) + tid;
    const uint4* gV = reinterpret_cast<const uint4*>(V + (size_t)head * S_LEN * DH) + tid;
    const uint32_t off = (uint32_t)(tid * 16) ^ (uint32_t)(((tid >> 3) & 1) << 4);
#pragma unroll
    for (int c = 0; c < EARLY; c++) {
        cp_async16(sK + c * 8192 + off, gK + c * 512);
        cp_async16(sV + c * 8192 + off, gV + c * 512);
        asm volatile("cp.async.commit_group;" ::: "memory");
    }
    if (tid < 128) asm volatile("st.shared.b32 [%0], %1;" :: "r"(sV + V_BYTES + tid * 4), "r"(0x3F803F80u) : "memory");
#pragma unroll
    for (int i = 0; i < 4; i++) qa[i] = scale_bf16x2(qa[i], qscale);
    const uint64_t descK0 = make_desc(sK, 16, 256);
    const uint64_t descV0 = make_desc(sV, V_BYTES, 256);
    float bias = __uint_as_float(127u * 128u - 77u);
    uint32_t chalf = 0x3F003F00u, cmu = 0x00030003u;
    asm volatile("" : "+f"(bias), "+r"(chalf), "+r"(cmu));

    asm volatile("cp.async.wait_group %0;" :: "n"(EARLY - 1) : "memory");
    asm volatile("fence.proxy.async.shared::cta;" ::: "memory");
    __syncthreads();
#pragma unroll
    for (int c = EARLY; c < 8; c++) {
        cp_async16(sK + c * 8192 + off, gK + c * 512);
        cp_async16(sV + c * 8192 + off, gV + c * 512);
        asm volatile("cp.async.commit_group;" ::: "memory");
    }
    qb[0] = __ldg(q32 + 512 + t); qb[1] = __ldg(q32 + 512 + 64 + t); qb[2] = __ldg(q32 + 512 + 4 + t); qb[3] = __ldg(q32 + 512 + 64 + 4 + t);

#pragma unroll 1
    for (int mt = 0; mt < 2; mt++) {
        float S[32]; uint32_t Pa[16], Pb[16];
        float Oa[12];
#pragma unroll
        for (int i = 0; i < 12; i++) Oa[i] = 0.f;

        wg_fence();
        wgmma_qk_n64_bf16(S, qa, descK0);
        wg_commit();
        wg_wait<0>();
        fence_f(S);
        process_block<0>(S, Pa, bias, chalf, cmu);
        fence_u(Pa);

#pragma unroll 1
        for (int sb = 0; sb < 8; sb++) {
            const uint64_t descK = descK0 + (uint64_t)(sb * 512);
            const uint64_t descV = descV0 + (uint64_t)sb * 16 * VSTEP;
            STEP(0, Pa, 1, Pb, 128)
            STEP(1, Pb, 2, Pa, 256)
            STEP(2, Pa, 3, Pb, 384)
            if (sb < 7) {
                if (mt == 0) {
                    asm volatile("cp.async.commit_group;\ncp.async.wait_group 7;" ::: "memory");
                    asm volatile("fence.proxy.async.shared::cta;" ::: "memory");
                    __syncthreads();
                } else if (SYNC2) {
                    __syncthreads();
                }
                STEP(3, Pb, 0, Pa, 512)
            } else {
                wg_fence();
                issue_pv(Oa, Pb, descV + 12 * VSTEP);
                wg_commit();
                wg_wait<0>();
                fence_u(Pb);
            }
        }
        fence_f(Oa);
        bool bad = !(Oa[8] >= 8.673617379884035e-19f && Oa[8] <= 1.2089258196146292e24f) ||
                   !(Oa[10] >= 8.673617379884035e-19f && Oa[10] <= 1.2089258196146292e24f);
        uint32_t* o32 = reinterpret_cast<uint32_t*>(O + (rowbase + mt * 64) * DH);
        if (__any_sync(0xffffffffu, bad)) {
            safe_rows(q32 + mt * 512, reinterpret_cast<const uint32_t*>(K + (size_t)head * S_LEN * DH),
                      reinterpret_cast<const unsigned short*>(V + (size_t)head * S_LEN * DH), o32);
        } else {
            const float r0 = 1.0f / Oa[8], r1 = 1.0f / Oa[10];
#pragma unroll
            for (int j = 0; j < 2; j++) {
                o32[j * 4 + t] = pack_bf16x2(Oa[4 * j] * r0, Oa[4 * j + 1] * r0);
                o32[64 + j * 4 + t] = pack_bf16x2(Oa[4 * j + 2] * r1, Oa[4 * j + 3] * r1);
            }
        }
#pragma unroll
        for (int i = 0; i < 4; i++) qa[i] = scale_bf16x2(qb[i], qscale);
    }
}

}

extern "C" void kernel_launch(void* const* d_in, const int* in_sizes, int n_in, void* d_out, int out_size) {
    const __nv_bfloat16* q = (const __nv_bfloat16*)d_in[0];
    const __nv_bfloat16* k = (const __nv_bfloat16*)d_in[1];
    const __nv_bfloat16* v = (const __nv_bfloat16*)d_in[2];
    __nv_bfloat16* o = (__nv_bfloat16*)d_out;
    cudaFuncSetAttribute(attn_kernel, cudaFuncAttributeMaxDynamicSharedMemorySize, SMEM_BYTES);
    attn_kernel<<<NHEAD * (S_LEN / ROWS_PER_CTA), NTHREADS, SMEM_BYTES>>>(q, k, v, o);
}
```

```cpp
#include <cuda_runtime.h>
#include <cuda_bf16.h>
#include <cuda_fp16.h>
#include <stdint.h>

#define NMUFU 20

namespace {

constexpr int S_LEN = 2048;
constexpr int DH = 16;
constexpr int NHEAD = 32;
constexpr int ROWS_PER_CTA = 512;
constexpr int NTHREADS = 512;
constexpr int K_BYTES = S_LEN * DH * 2;
constexpr int V_BYTES = S_LEN * DH * 2;
constexpr int ONES_BYTES = 512;
constexpr int SMEM_BYTES = K_BYTES + V_BYTES + ONES_BYTES + 256;

__device__ __forceinline__ void wg_fence() { asm volatile("wgmma.fence.sync.aligned;" ::: "memory"); }
__device__ __forceinline__ void wg_commit() { asm volatile("wgmma.commit_group.sync.aligned;" ::: "memory"); }
template<int N> __device__ __forceinline__ void wg_wait() { asm volatile("wgmma.wait_group.sync.aligned %0;" :: "n"(N) : "memory"); }

__device__ __forceinline__ uint64_t make_desc(uint32_t saddr, uint32_t lbo, uint32_t sbo) {
    return (uint64_t)((saddr & 0x3FFFF) >> 4) | ((uint64_t)((lbo & 0x3FFFF) >> 4) << 16) | ((uint64_t)((sbo & 0x3FFFF) >> 4) << 32) | (3ull << 62);
}
template<int N> __device__ __forceinline__ void fence_u(uint32_t (&a)[N]) {
#pragma unroll
    for (int i = 0; i < N; i++) asm volatile("" : "+r"(a[i]) :: "memory");
}

__device__ __forceinline__ void wgmma_qk(uint32_t (&d)[16], const uint32_t (&a)[4], uint64_t descB) {
    asm volatile("{\n.reg .pred p;\nsetp.ne.b32 p, 0, 0;\n"
        "wgmma.mma_async.sync.aligned.m64n64k16.f16.f16.f16 {%0, %1, %2, %3, %4, %5, %6, %7, %8, %9, %10, %11, %12, %13, %14, %15}, {%16, %17, %18, %19}, %20, p, 1, 1, 0;\n}\n"
        : "=r"(d[0]), "=r"(d[1]), "=r"(d[2]), "=r"(d[3]), "=r"(d[4]), "=r"(d[5]), "=r"(d[6]), "=r"(d[7]),
          "=r"(d[8]), "=r"(d[9]), "=r"(d[10]), "=r"(d[11]), "=r"(d[12]), "=r"(d[13]), "=r"(d[14]), "=r"(d[15])
        : "r"(a[0]), "r"(a[1]), "r"(a[2]), "r"(a[3]), "l"(descB));
}
__device__ __forceinline__ void wgmma_pv(uint32_t (&d)[6], uint32_t a0, uint32_t a1, uint32_t a2, uint32_t a3, uint64_t descB, int acc) {
    asm volatile("{\n.reg .pred p;\nsetp.ne.b32 p, %11, 0;\n"
        "wgmma.mma_async.sync.aligned.m64n24k16.f16.f16.f16 {%0, %1, %2, %3, %4, %5}, {%6, %7, %8, %9}, %10, p, 1, 1, 1;\n}\n"
        : "+r"(d[0]), "+r"(d[1]), "+r"(d[2]), "+r"(d[3]), "+r"(d[4]), "+r"(d[5])
        : "r"(a0), "r"(a1), "r"(a2), "r"(a3), "l"(descB), "r"(acc));
}

__device__ __forceinline__ float ex2f(float x) { float e; asm("ex2.approx.ftz.f32 %0, %1;" : "=f"(e) : "f"(x)); return e; }
__device__ __forceinline__ uint32_t pack_bf16x2(float lo, float hi) {
    uint32_t r; asm("cvt.rn.bf16x2.f32 %0, %1, %2;" : "=r"(r) : "f"(hi), "f"(lo)); return r;
}
__device__ __forceinline__ uint32_t pack_f16x2(float lo, float hi) {
    uint32_t r; asm("cvt.rn.f16x2.f32 %0, %1, %2;" : "=r"(r) : "f"(hi), "f"(lo)); return r;
}
__device__ __forceinline__ float bf_lo(uint32_t x) { return __uint_as_float(x << 16); }
__device__ __forceinline__ float bf_hi(uint32_t x) { return __uint_as_float(x & 0xFFFF0000u); }
__device__ __forceinline__ uint32_t bf16x2_to_f16x2(uint32_t x) { return pack_f16x2(bf_lo(x), bf_hi(x)); }
__device__ __forceinline__ uint32_t hfma2(uint32_t a, uint32_t b, uint32_t c) {
    uint32_t r; asm("fma.rn.f16x2 %0, %1, %2, %3;" : "=r"(r) : "r"(a), "r"(b), "r"(c)); return r;
}

__device__ __forceinline__ uint32_t exp_mufu(uint32_t s) {
    uint32_t r; asm("ex2.approx.f16x2 %0, %1;" : "=r"(r) : "r"(s)); return r;
}
__device__ __forceinline__ uint32_t exp_poly(uint32_t s, uint32_t bp, uint32_t c0, uint32_t c1) {
    uint32_t y, z, e;
    asm("fma.rn.relu.f16x2 %0, %1, %2, %3;" : "=r"(y) : "r"(s), "r"(0x00400040u), "r"(bp));
    uint32_t pl = y << 4;
    asm("lop3.b32 %0, %1, 0x03FF03FF, %2, 0xEA;" : "=r"(z) : "r"(pl), "r"(c0));
    asm("lop3.b32 %0, %1, 0xFC00FC00, %2, 0xEA;" : "=r"(e) : "r"(pl), "r"(c1));
    return hfma2(pl, z, e);
}
__host__ __device__ constexpr bool reg_is_mufu(int r) { return ((r + 1) * NMUFU) / 64 != (r * NMUFU) / 64; }

template<int IDX>
__device__ __forceinline__ void process_block(const uint32_t (&S)[16], uint32_t (&P)[16], const uint32_t (&cs)[6]) {
#pragma unroll
    for (int r = 0; r < 16; r++) {
        const int o = (r & 1) ^ 1;
        if (reg_is_mufu(IDX * 16 + r)) P[r] = exp_mufu(S[r]);
        else                           P[r] = exp_poly(S[r], cs[o], cs[2 + o], cs[4 + o]);
    }
}
constexpr uint64_t VSTEP = 32ull - (32ull << 16);

__device__ __forceinline__ void issue_pv(uint32_t (&Oh)[6], const uint32_t (&P)[16], uint64_t descV, int acc) {
#pragma unroll
    for (int ks = 0; ks < 4; ks++) wgmma_pv(Oh, P[ks * 4], P[ks * 4 + 1], P[ks * 4 + 2], P[ks * 4 + 3], descV + ks * VSTEP, ks == 0 ? acc : 1);
}
__device__ __forceinline__ void flush_acc(const uint32_t (&Oh)[6], uint32_t (&Om)[6]) {
#pragma unroll
    for (int i = 0; i < 6; i++) asm("add.rn.f16x2 %0, %0, %1;" : "+r"(Om[i]) : "r"(Oh[i]));
}
__device__ __forceinline__ void final_acc(const uint32_t (&Oh)[6], const uint32_t (&Om)[6], float (&M)[10], bool use_h) {
#pragma unroll
    for (int i = 0; i < 4; i++) {
        float2 f = __half22float2(*reinterpret_cast<const __half2*>(&Om[i]));
        if (use_h) { float2 e = __half22float2(*reinterpret_cast<const __half2*>(&Oh[i])); f.x += e.x; f.y += e.y; }
        M[2 * i] = f.x; M[2 * i + 1] = f.y;
    }
    M[8] = __low2float(*reinterpret_cast<const __half2*>(&Om[4])); M[9] = __low2float(*reinterpret_cast<const __half2*>(&Om[5]));
    if (use_h) { M[8] += __low2float(*reinterpret_cast<const __half2*>(&Oh[4])); M[9] += __low2float(*reinterpret_cast<const __half2*>(&Oh[5])); }
}

#define STEP(IDX, QA, OPREV, PPREV, PCUR, DK, DV, ACC) \
    wg_fence(); \
    wgmma_qk(S, QA, DK); \
    wg_commit(); \
    issue_pv(OPREV, PPREV, DV, ACC); \
    wg_commit(); \
    wg_wait<1>(); \
    fence_u(S); fence_u(PCUR); \
    process_block<IDX>(S, PCUR, cs); \
    fence_u(PCUR);

__device__ __forceinline__ void mma_bf16(float (&d)[4], const uint32_t (&a)[4], uint32_t b0, uint32_t b1) {
    asm volatile("mma.sync.aligned.m16n8k16.row.col.f32.bf16.bf16.f32 {%0,%1,%2,%3}, {%4,%5,%6,%7}, {%8,%9}, {%0,%1,%2,%3};"
                 : "+f"(d[0]), "+f"(d[1]), "+f"(d[2]), "+f"(d[3]) : "r"(a[0]), "r"(a[1]), "r"(a[2]), "r"(a[3]), "r"(b0), "r"(b1));
}
__device__ __noinline__ void safe_rows(const uint32_t* __restrict__ q32, const uint32_t* __restrict__ k32,
                                       const unsigned short* __restrict__ v16, uint32_t* __restrict__ o32) {
    const int lane = threadIdx.x & 31, g = lane >> 2, t = lane & 3;
    const float c = 0.25f * 1.4426950408889634f;
    uint32_t qa[4] = {q32[t], q32[64 + t], q32[4 + t], q32[64 + 4 + t]};
    float m0 = -INFINITY, m1 = -INFINITY, l0 = 0.f, l1 = 0.f;
    float o0[4] = {0.f, 0.f, 0.f, 0.f}, o1[4] = {0.f, 0.f, 0.f, 0.f};
#pragma unroll 1
    for (int k0 = 0; k0 < S_LEN; k0 += 16) {
        float sa[4] = {0.f, 0.f, 0.f, 0.f}, sb[4] = {0.f, 0.f, 0.f, 0.f};
        mma_bf16(sa, qa, k32[(k0 + g) * 8 + t], k32[(k0 + g) * 8 + 4 + t]);
        mma_bf16(sb, qa, k32[(k0 + 8 + g) * 8 + t], k32[(k0 + 8 + g) * 8 + 4 + t]);
#pragma unroll
        for (int i = 0; i < 4; i++) { sa[i] *= c; sb[i] *= c; }
        float n0 = fmaxf(fmaxf(sa[0], sa[1]), fmaxf(sb[0], sb[1])), n1 = fmaxf(fmaxf(sa[2], sa[3]), fmaxf(sb[2], sb[3]));
        n0 = fmaxf(n0, __shfl_xor_sync(0xffffffffu, n0, 1)); n0 = fmaxf(n0, __shfl_xor_sync(0xffffffffu, n0, 2));
        n1 = fmaxf(n1, __shfl_xor_sync(0xffffffffu, n1, 1)); n1 = fmaxf(n1, __shfl_xor_sync(0xffffffffu, n1, 2));
        n0 = fmaxf(n0, m0); n1 = fmaxf(n1, m1);
        const float u0 = (n0 == -INFINITY) ? 0.f : n0, u1 = (n1 == -INFINITY) ? 0.f : n1;
        const float c0 = ex2f(m0 - u0), c1 = ex2f(m1 - u1);
        m0 = n0; m1 = n1;
        uint32_t pa[4];
        pa[0] = pack_bf16x2(ex2f(sa[0] - u0), ex2f(sa[1] - u0)); pa[1] = pack_bf16x2(ex2f(sa[2] - u1), ex2f(sa[3] - u1));
        pa[2] = pack_bf16x2(ex2f(sb[0] - u0), ex2f(sb[1] - u0)); pa[3] = pack_bf16x2(ex2f(sb[2] - u1), ex2f(sb[3] - u1));
        l0 = l0 * c0 + (bf_lo(pa[0]) + bf_hi(pa[0]) + bf_lo(pa[2]) + bf_hi(pa[2]));
        l1 = l1 * c1 + (bf_lo(pa[1]) + bf_hi(pa[1]) + bf_lo(pa[3]) + bf_hi(pa[3]));
        o0[0] *= c0; o0[1] *= c0; o0[2] *= c1; o0[3] *= c1;
        o1[0] *= c0; o1[1] *= c0; o1[2] *= c1; o1[3] *= c1;
        const unsigned short* vp = v16 + (k0 + 2 * t) * 16 + g;
        mma_bf16(o0, pa, (uint32_t)vp[0] | ((uint32_t)vp[16] << 16), (uint32_t)vp[128] | ((uint32_t)vp[144] << 16));
        mma_bf16(o1, pa, (uint32_t)vp[8] | ((uint32_t)vp[24] << 16), (uint32_t)vp[136] | ((uint32_t)vp[152] << 16));
    }
    l0 += __shfl_xor_sync(0xffffffffu, l0, 1); l0 += __shfl_xor_sync(0xffffffffu, l0, 2);
    l1 += __shfl_xor_sync(0xffffffffu, l1, 1); l1 += __shfl_xor_sync(0xffffffffu, l1, 2);
    const float r0 = 1.0f / l0, r1 = 1.0f / l1;
    o32[t] = pack_bf16x2(o0[0] * r0, o0[1] * r0);       o32[64 + t] = pack_bf16x2(o0[2] * r1, o0[3] * r1);
    o32[4 + t] = pack_bf16x2(o1[0] * r0, o1[1] * r0);   o32[64 + 4 + t] = pack_bf16x2(o1[2] * r1, o1[3] * r1);
}

__device__ __forceinline__ void finish_tile(const float (&M)[10], bool unsafe, float lmin, const uint32_t* q32, const __nv_bfloat16* K,
                                            const __nv_bfloat16* V, __nv_bfloat16* O, size_t row, int head, int t) {
    float r0, r1;
    asm("rcp.approx.ftz.f32 %0, %1;" : "=f"(r0) : "f"(M[8]));
    asm("rcp.approx.ftz.f32 %0, %1;" : "=f"(r1) : "f"(M[9]));
    const float chk = fabsf(M[0]) + fabsf(M[1]) + fabsf(M[2]) + fabsf(M[3]) + fabsf(M[4]) + fabsf(M[5]) + fabsf(M[6]) + fabsf(M[7]) + M[8] + M[9];
    bool bad = unsafe || !(chk < 1e30f) || !(M[8] >= lmin) || !(M[9] >= lmin);
    uint32_t* o32 = reinterpret_cast<uint32_t*>(O + row * DH);
    if (__any_sync(0xffffffffu, bad)) {
        safe_rows(q32, reinterpret_cast<const uint32_t*>(K + (size_t)head * S_LEN * DH),
                  reinterpret_cast<const unsigned short*>(V + (size_t)head * S_LEN * DH), o32);
    } else {
        o32[t] = pack_bf16x2(M[0] * r0, M[1] * r0);     o32[64 + t] = pack_bf16x2(M[2] * r1, M[3] * r1);
        o32[4 + t] = pack_bf16x2(M[4] * r0, M[5] * r0); o32[68 + t] = pack_bf16x2(M[6] * r1, M[7] * r1);
    }
}

__device__ __forceinline__ float prep_q(uint32_t (&qa)[4], float qscale) {
    float f[8];
#pragma unroll
    for (int i = 0; i < 4; i++) { f[2 * i] = bf_lo(qa[i]) * qscale; f[2 * i + 1] = bf_hi(qa[i]) * qscale; qa[i] = pack_f16x2(f[2 * i], f[2 * i + 1]); }
    float n0 = f[0] * f[0] + f[1] * f[1] + f[4] * f[4] + f[5] * f[5];
    float n1 = f[2] * f[2] + f[3] * f[3] + f[6] * f[6] + f[7] * f[7];
    n0 += __shfl_xor_sync(0xffffffffu, n0, 1); n0 += __shfl_xor_sync(0xffffffffu, n0, 2);
    n1 += __shfl_xor_sync(0xffffffffu, n1, 1); n1 += __shfl_xor_sync(0xffffffffu, n1, 2);
    return (n0 > n1 || n0 != n0) ? n0 : n1;
}

__device__ __forceinline__ void cvt4(uint4& a) {
    a.x = bf16x2_to_f16x2(a.x); a.y = bf16x2_to_f16x2(a.y); a.z = bf16x2_to_f16x2(a.z); a.w = bf16x2_to_f16x2(a.w);
}
__device__ __forceinline__ void sts4(uint32_t addr, const uint4& a) {
    asm volatile("st.shared.v4.b32 [%0], {%1,%2,%3,%4};" :: "r"(addr), "r"(a.x), "r"(a.y), "r"(a.z), "r"(a.w) : "memory");
}
__device__ __forceinline__ uint32_t sumsq4(const uint4& a) { return hfma2(a.x, a.x, hfma2(a.y, a.y, hfma2(a.z, a.z, hfma2(a.w, a.w, 0u)))); }
__device__ __forceinline__ uint32_t habsmax3(uint32_t m, uint32_t a, uint32_t b) {
    __half2 x = __hmax2_nan(__habs2(*reinterpret_cast<__half2*>(&a)), __habs2(*reinterpret_cast<__half2*>(&b)));
    x = __hmax2_nan(x, *reinterpret_cast<__half2*>(&m));
    return *reinterpret_cast<uint32_t*>(&x);
}
__device__ __forceinline__ void convert_batch(uint4 k0, uint4 k1, uint4 v0, uint4 v1, uint32_t dK, uint32_t dV, uint32_t& kn, uint32_t& vm) {
    cvt4(k0); cvt4(k1); cvt4(v0); cvt4(v1);
    sts4(dK, k0); sts4(dK + 8192, k1); sts4(dV, v0); sts4(dV + 8192, v1);
    const uint32_t s0 = sumsq4(k0), s1 = sumsq4(k1);
    const uint32_t lo = __byte_perm(s0, s1, 0x5410), hi = __byte_perm(s0, s1, 0x7632);
    __half2 h = __hadd2(*reinterpret_cast<const __half2*>(&lo), *reinterpret_cast<const __half2*>(&hi));
    uint32_t u = *reinterpret_cast<uint32_t*>(&h);
    uint32_t w = __shfl_xor_sync(0xffffffffu, u, 1);
    h = __hadd2(h, *reinterpret_cast<__half2*>(&w));
    kn = __vmaxu2(kn, *reinterpret_cast<uint32_t*>(&h));
    vm = habsmax3(vm, v0.x, v0.y); vm = habsmax3(vm, v0.z, v0.w); vm = habsmax3(vm, v1.x, v1.y); vm = habsmax3(vm, v1.z, v1.w);
}

__global__ void __launch_bounds__(NTHREADS, 1)
attn_kernel(const __nv_bfloat16* __restrict__ Q, const __nv_bfloat16* __restrict__ K,
            const __nv_bfloat16* __restrict__ V, __nv_bfloat16* __restrict__ O) {
    extern __shared__ __align__(1024) uint8_t smem[];
    const int tid = threadIdx.x;
    const int head = blockIdx.x >> 2;
    const int rb = blockIdx.x & 3;
    const uint32_t sK = (uint32_t)__cvta_generic_to_shared(smem);
    const uint32_t sV = sK + K_BYTES;
    uint32_t* sRed = reinterpret_cast<uint32_t*>(smem + K_BYTES + V_BYTES + ONES_BYTES);
    const uint4* gK = reinterpret_cast<const uint4*>(K + (size_t)head * S_LEN * DH) + tid;
    const uint4* gV = reinterpret_cast<const uint4*>(V + (size_t)head * S_LEN * DH) + tid;
    const int wg = __shfl_sync(0xffffffffu, tid >> 7, 0), warp = (tid >> 5) & 3, lane = tid & 31;
    const int g = lane >> 2, t = lane & 3;
    const size_t rowbase = (size_t)head * S_LEN + rb * ROWS_PER_CTA + wg * 128 + warp * 16 + g;
    const uint32_t* q32 = reinterpret_cast<const uint32_t*>(Q + rowbase * DH);
    uint32_t qa[4], qb[4];
    qa[0] = __ldg(q32 + t); qa[1] = __ldg(q32 + 64 + t); qa[2] = __ldg(q32 + 4 + t); qa[3] = __ldg(q32 + 64 + 4 + t);
    qb[0] = __ldg(q32 + 512 + t); qb[1] = __ldg(q32 + 512 + 64 + t); qb[2] = __ldg(q32 + 512 + 4 + t); qb[3] = __ldg(q32 + 512 + 64 + 4 + t);

    uint4 kr[8], vr[8];
#pragma unroll
    for (int c = 0; c < 4; c++) {
        kr[2 * c] = __ldg(gK + c * 1024); kr[2 * c + 1] = __ldg(gK + c * 1024 + 512);
        vr[2 * c] = __ldg(gV + c * 1024); vr[2 * c + 1] = __ldg(gV + c * 1024 + 512);
    }
    if (tid >= 128 && tid < 256) asm volatile("st.shared.b32 [%0], %1;" :: "r"(sV + V_BYTES + (tid - 128) * 4), "r"(0x3C003C00u) : "memory");
    const float qscale = 0.25f * 1.4426950408889634f;
    const float qna = prep_q(qa, qscale), qnb = prep_q(qb, qscale);
    {
        const uint32_t offs = (uint32_t)(tid * 16) ^ (uint32_t)(((tid >> 3) & 1) << 4);
        uint32_t kn = 0u, vm = 0u;
#pragma unroll
        for (int c = 0; c < 4; c++)
            convert_batch(kr[2 * c], kr[2 * c + 1], vr[2 * c], vr[2 * c + 1], sK + c * 16384 + offs, sV + c * 16384 + offs, kn, vm);
        const uint32_t a = __reduce_max_sync(0xffffffffu, max(kn & 0xFFFFu, kn >> 16));
        const uint32_t c = __reduce_max_sync(0xffffffffu, max(vm & 0xFFFFu, vm >> 16));
        if (lane == 0) { sRed[(tid >> 5) * 2] = a; sRed[(tid >> 5) * 2 + 1] = c; }
    }
    if (tid < 6) sRed[32 + tid] = tid < 2 ? (922u | (922u << 16)) : tid < 4 ? 0x38003800u : 0x000B000Bu;
    asm volatile("fence.proxy.async.shared::cta;" ::: "memory");
    __syncthreads();

    const uint64_t descK0 = make_desc(sK, 16, 256);
    const uint64_t descV0 = make_desc(sV, V_BYTES, 256);
    uint32_t cs[6];
    asm volatile("ld.shared.v4.b32 {%0,%1,%2,%3}, [%4];" : "=r"(cs[0]), "=r"(cs[1]), "=r"(cs[2]), "=r"(cs[3]) : "r"(sV + V_BYTES + ONES_BYTES + 128) : "memory");
    asm volatile("ld.shared.v2.b32 {%0,%1}, [%2];" : "=r"(cs[4]), "=r"(cs[5]) : "r"(sV + V_BYTES + ONES_BYTES + 144) : "memory");

    uint32_t S[16], Pa[16], Pb[16];
    uint32_t Oa[6], Ob[6];
    uint32_t Ma[6], Mb[6];
#pragma unroll
    for (int i = 0; i < 6; i++) { Oa[i] = 0u; Ob[i] = 0u; }
#pragma unroll
    for (int i = 0; i < 6; i++) { Ma[i] = 0; Mb[i] = 0; }
#pragma unroll
    for (int i = 0; i < 16; i++) { Pb[i] = 0u; Pa[i] = 0u; }
    uint64_t descK = descK0, descV = descV0, descVp = descV0;
#pragma unroll 1
    for (int it = 0; it < 16; it++) {
        STEP(0, qa, Ob, Pb, Pa, descK, descVp, 0)
        STEP(1, qb, Oa, Pa, Pb, descK, descV, 0)
        STEP(2, qa, Ob, Pb, Pa, descK + 128, descV, 1)
        STEP(3, qb, Oa, Pa, Pb, descK + 128, descV + 4 * VSTEP, 1)
        descVp = descV + 4 * VSTEP;
        descV += 8 * VSTEP;
        descK += 256;
        wg_wait<0>();
        fence_u(Pa);
        fence_u(Oa); fence_u(Ob);
        flush_acc(Oa, Ma); flush_acc(Ob, Mb);
        fence_u(Oa); fence_u(Ob);
    }
    wg_fence();
    issue_pv(Ob, Pb, descVp, 0);
    wg_commit();
    wg_wait<0>();
    fence_u(Pb);
    fence_u(Ob); fence_u(Oa);
    float Fa[10], Fb[10];
    final_acc(Oa, Ma, Fa, false); final_acc(Ob, Mb, Fb, true);
    bool unsafe_a, unsafe_b;
    float lmin_a, lmin_b;
    {
        const uint32_t x = sRed[lane];
        const uint32_t a = __reduce_max_sync(0xffffffffu, (lane & 1) ? 0u : x), c = __reduce_max_sync(0xffffffffu, (lane & 1) ? x : 0u);
        const float kn2 = __half2float(__ushort_as_half((unsigned short)a)) * 1.02f;
        const float vmax = __half2float(__ushort_as_half((unsigned short)c));
        const bool ok = (kn2 <= 60000.f) && (vmax >= 0.001953125f) && (vmax <= 16384.f);
        const float ra = qna * kn2, rb2 = qnb * kn2, lmin = __fdividef(0.0625f, vmax);
        unsafe_a = !(ok && ra <= 295.f && qna <= 60000.f);
        unsafe_b = !(ok && rb2 <= 295.f && qnb <= 60000.f);
        lmin_a = (ra <= 176.f) ? lmin : fmaxf(lmin, 128.f);
        lmin_b = (rb2 <= 176.f) ? lmin : fmaxf(lmin, 128.f);
    }
    finish_tile(Fa, unsafe_a, lmin_a, q32, K, V, O, rowbase, head, t);
    finish_tile(Fb, unsafe_b, lmin_b, q32 + 512, K, V, O, rowbase + 64, head, t);
}

}

extern "C" void kernel_launch(void* const* d_in, const int* in_sizes, int n_in, void* d_out, int out_size) {
    const __nv_bfloat16* q = (const __nv_bfloat16*)d_in[0];
    const __nv_bfloat16* k = (const __nv_bfloat16*)d_in[1];
    const __nv_bfloat16* v = (const __nv_bfloat16*)d_in[2];
    __nv_bfloat16* o = (__nv_bfloat16*)d_out;
    cudaFuncSetAttribute(attn_kernel, cudaFuncAttributeMaxDynamicSharedMemorySize, SMEM_BYTES);
    attn_kernel<<<NHEAD * (S_LEN / ROWS_PER_CTA), NTHREADS, SMEM_BYTES>>>(q, k, v, o);
}
```
